```python
import torch

def _softmax(x, axis=-1):
    return torch.softmax(x, dim=axis)
def _gelu(x):
    return torch.nn.functional.gelu(x, approximate="tanh")
def _silu(x):
    return torch.nn.functional.silu(x)
def _sigmoid(x):
    return torch.sigmoid(x)
def _layernorm(x, axis=-1, eps=1e-5):
    m = x.mean(dim=axis, keepdim=True)
    v = x.var(dim=axis, keepdim=True, unbiased=False)
    return (x - m) / torch.sqrt(v + eps)
def _scatter_add(tgt, idx, src, axis=0):
    return tgt.clone().index_add_(axis, idx, src)
def _segment_sum(src, seg, n):
    out = torch.zeros((n,) + src.shape[1:], dtype=src.dtype)
    return out.index_add_(0, seg, src)
def _pad(x, pw):
    flat = tuple(v for pair in reversed(pw) for v in pair)
    return torch.nn.functional.pad(x, flat)

kernel_name = 'standalone__gqa_softmax__near_ridge'

def setup_inputs():

    _w = (lambda a: (lambda t: t.to(torch.bfloat16) if t.is_floating_point() else t)(torch.as_tensor(a)))
    B, Hq, Hkv, Sq, Sk, D = 16, 32, 8, 512, 512, 128
    return {
        "q": _w((lambda *s: torch.randn(*s, dtype=torch.bfloat16) * 0.8)(B, Hq, Sq, D)),
        "k": _w((lambda *s: torch.randn(*s, dtype=torch.bfloat16) * 0.8)(B, Hkv, Sk, D)),
        "v": _w((lambda *s: torch.randn(*s, dtype=torch.bfloat16) * 0.05)(B, Hkv, Sk, D)),
    }

def reference(q, k, v):
    B, Hq, Sq, D = q.shape
    Hkv = k.shape[1]
    rep = Hq // Hkv
    k = (lambda x, n, axis: torch.repeat_interleave(x, n, dim=axis))(k, rep, axis=1)
    v = (lambda x, n, axis: torch.repeat_interleave(x, n, dim=axis))(v, rep, axis=1)
    scale = D ** -0.5
    scores = torch.einsum("bhqd,bhkd->bhqk", q, k) * scale
    p = _softmax(scores, axis=-1)
    return torch.einsum("bhqk,bhkd->bhqd", p, v)
```

```cpp
#include <cuda_runtime.h>
#include <cuda_bf16.h>
#include <cuda.h>
#include <stdint.h>

#define DEF    8
#define DEF0   4
#define GP     2
#define GPB_Q  1
#define SDELAY 400

namespace {

constexpr int kSeq   = 512;
constexpr int kD     = 128;
constexpr int kBlkN  = 128;
constexpr int kNBlk  = kSeq / kBlkN;
constexpr int kItems = 4;
constexpr int kTilesPerItem = 4;
constexpr int kTiles = kItems * kTilesPerItem;
constexpr int kGrid  = 128;
__host__ __device__ constexpr int j0_of(int blk) { return 16 - (blk == 0 ? DEF0 : DEF); }
__host__ __device__ constexpr int pv_groups(int j0) { return (j0 > 0 ? 1 : 0) + ((16 - j0) / 2 + GP - 1) / GP; }
constexpr int KS = 4, VS = 2;
constexpr uint32_t kBlkBytes = kBlkN * kD * 2;
constexpr uint32_t kWgQBytes = 64 * kD * 2;

constexpr uint32_t kOffK = 0;
constexpr uint32_t kOffV = kOffK + KS * kBlkBytes;
constexpr uint32_t kOffQ = kOffV + VS * kBlkBytes;
constexpr uint32_t kOffBar = kOffQ + 2 * kWgQBytes;
constexpr uint32_t kSmemBytes = kOffBar + 256;
static_assert(kSmemBytes <= 232448, "smem");

constexpr uint32_t kBarKFull = 0, kBarKEmpty = kBarKFull + KS, kBarVFull = kBarKEmpty + KS,
                   kBarVEmpty = kBarVFull + VS, kBarQFull = kBarVEmpty + VS, kBarOFull = kBarQFull + 2,
                   kNumBars = kBarOFull + 2;
static_assert(kNumBars * 8 <= 256, "bars");

template <int V> struct IC { static constexpr int value = V; };

__device__ __forceinline__ uint32_t smem_u32(const void* p) { return (uint32_t)__cvta_generic_to_shared(p); }

__device__ __forceinline__ void mbar_init(uint32_t a, uint32_t cnt) {
    asm volatile("mbarrier.init.shared::cta.b64 [%0], %1;" ::"r"(a), "r"(cnt) : "memory");
}
__device__ __forceinline__ void mbar_expect_tx(uint32_t a, uint32_t bytes) {
    asm volatile("mbarrier.arrive.expect_tx.shared::cta.b64 _, [%0], %1;" ::"r"(a), "r"(bytes) : "memory");
}
__device__ __forceinline__ void mbar_arrive(uint32_t a) {
    asm volatile("mbarrier.arrive.shared::cta.b64 _, [%0];" ::"r"(a) : "memory");
}
__device__ __forceinline__ bool mbar_try(uint32_t a, uint32_t parity) {
    uint32_t ok;
    asm volatile(
        "{\n.reg .pred p;\n"
        "mbarrier.try_wait.parity.shared::cta.b64 p, [%1], %2;\n"
        "selp.u32 %0, 1, 0, p;\n}\n"
        : "=r"(ok) : "r"(a), "r"(parity) : "memory");
    return ok != 0;
}
__device__ __forceinline__ void mbar_wait(uint32_t a, uint32_t parity) {
    asm volatile(
        "{\n.reg .pred p;\n.reg .u32 c;\n"
        "mov.u32 c, 0;\n"
        "LAB_WAIT:\n"
        "mbarrier.try_wait.parity.shared::cta.b64 p, [%0], %1;\n"
        "@p bra LAB_DONE;\n"
        "add.u32 c, c, 1;\n"
        "setp.lt.u32 p, c, 4000000;\n"
        "@p bra LAB_WAIT;\n"
        "trap;\n"
        "LAB_DONE:\n}\n"
        ::"r"(a), "r"(parity) : "memory");
}

__device__ __forceinline__ void tma_load_3d(uint32_t dst, const CUtensorMap* tm, uint32_t bar, int c0, int c1, int c2) {
    asm volatile(
        "cp.async.bulk.tensor.3d.shared::cluster.global.mbarrier::complete_tx::bytes [%0], [%1, {%3, %4, %5}], [%2];"
        ::"r"(dst), "l"(tm), "r"(bar), "r"(c0), "r"(c1), "r"(c2) : "memory");
}
__device__ __forceinline__ void bulk_prefetch(const void* src, uint32_t bytes) {
    asm volatile("cp.async.bulk.prefetch.L2.global [%0], %1;" ::"l"(src), "r"(bytes) : "memory");
}
__device__ __forceinline__ void tma_store_3d(const CUtensorMap* tm, uint32_t src, int c0, int c1, int c2) {
    asm volatile("cp.async.bulk.tensor.3d.global.shared::cta.bulk_group [%0, {%2, %3, %4}], [%1];"
                 ::"l"(tm), "r"(src), "r"(c0), "r"(c1), "r"(c2) : "memory");
}
__device__ __forceinline__ void bulk_commit() { asm volatile("cp.async.bulk.commit_group;" ::: "memory"); }
__device__ __forceinline__ void bulk_wait_read0() { asm volatile("cp.async.bulk.wait_group.read 0;" ::: "memory"); }
__device__ __forceinline__ void fence_async_smem() { asm volatile("fence.proxy.async.shared::cta;" ::: "memory"); }

__device__ __forceinline__ void bar_sync(int id, int n) { asm volatile("bar.sync %0, %1;" ::"r"(id), "r"(n) : "memory"); }
__device__ __forceinline__ void bar_arrive(int id, int n) { asm volatile("bar.arrive %0, %1;" ::"r"(id), "r"(n) : "memory"); }

__device__ __forceinline__ void sched_fence(int& zero) {
    asm volatile(
        "{\n.reg .pred p;\n"
        "LAB_SF:\n"
        "add.s32 %0, %0, %0;\n"
        "setp.lt.s32 p, %0, 0;\n"
        "@p bra.uni LAB_SF;\n}\n" : "+r"(zero)::"memory");
}
__device__ __forceinline__ void wg_fence() { asm volatile("wgmma.fence.sync.aligned;" ::: "memory"); }
__device__ __forceinline__ void wg_commit() { asm volatile("wgmma.commit_group.sync.aligned;" ::: "memory"); }
template <int N> __device__ __forceinline__ void wg_wait() {
    asm volatile("wgmma.wait_group.sync.aligned %0;" ::"n"(N) : "memory");
}

#define ACC8(d, i) "+f"(d[i]), "+f"(d[i + 1]), "+f"(d[i + 2]), "+f"(d[i + 3]), "+f"(d[i + 4]), "+f"(d[i + 5]), "+f"(d[i + 6]), "+f"(d[i + 7])
#define ACC64(d) ACC8(d, 0), ACC8(d, 8), ACC8(d, 16), ACC8(d, 24), ACC8(d, 32), ACC8(d, 40), ACC8(d, 48), ACC8(d, 56)
#define REGS64                                                                         \
    "{%0, %1, %2, %3, %4, %5, %6, %7, %8, %9, %10, %11, %12, %13, %14, %15, "          \
    "%16, %17, %18, %19, %20, %21, %22, %23, %24, %25, %26, %27, %28, %29, %30, %31, " \
    "%32, %33, %34, %35, %36, %37, %38, %39, %40, %41, %42, %43, %44, %45, %46, %47, " \
    "%48, %49, %50, %51, %52, %53, %54, %55, %56, %57, %58, %59, %60, %61, %62, %63}"

template <int TRANS_B>
__device__ __forceinline__ void wgmma_rs(float (&d)[64], uint32_t a0, uint32_t a1, uint32_t a2, uint32_t a3,
                                         uint64_t descB, int scale_d) {
    asm volatile(
        "{\n.reg .pred p;\n"
        "setp.ne.b32 p, %69, 0;\n"
        "wgmma.mma_async.sync.aligned.m64n128k16.f32.bf16.bf16 " REGS64 ", {%64, %65, %66, %67}, %68, p, 1, 1, %70;\n}\n"
        : ACC64(d)
        : "r"(a0), "r"(a1), "r"(a2), "r"(a3), "l"(descB), "r"(scale_d), "n"(TRANS_B));
}

#define OUT8(d, i) "=f"(d[i]), "=f"(d[i + 1]), "=f"(d[i + 2]), "=f"(d[i + 3]), "=f"(d[i + 4]), "=f"(d[i + 5]), "=f"(d[i + 6]), "=f"(d[i + 7])
#define OUT64(d) OUT8(d, 0), OUT8(d, 8), OUT8(d, 16), OUT8(d, 24), OUT8(d, 32), OUT8(d, 40), OUT8(d, 48), OUT8(d, 56)
__device__ __forceinline__ void wgmma_rs_init(float (&d)[64], uint32_t a0, uint32_t a1, uint32_t a2, uint32_t a3,
                                              uint64_t descB) {
    asm volatile(
        "{\n.reg .pred p;\n"
        "setp.ne.b32 p, 0, 0;\n"
        "wgmma.mma_async.sync.aligned.m64n128k16.f32.bf16.bf16 " REGS64 ", {%64, %65, %66, %67}, %68, p, 1, 1, 0;\n}\n"
        : OUT64(d)
        : "r"(a0), "r"(a1), "r"(a2), "r"(a3), "l"(descB));
}

__device__ __forceinline__ void fence_regs(float (&d)[64]) {
#pragma unroll
    for (int i = 0; i < 64; i++) asm volatile("" : "+f"(d[i])::"memory");
}
__device__ __forceinline__ void fence_regs(uint32_t (&d)[32]) {
#pragma unroll
    for (int i = 0; i < 32; i++) asm volatile("" : "+r"(d[i])::"memory");
}

__device__ __forceinline__ float ex2(float x) {
    float y;
    asm("ex2.approx.ftz.f32 %0, %1;" : "=f"(y) : "f"(x));
    return y;
}
__device__ __forceinline__ float rcp(float x) {
    float y;
    asm("rcp.approx.ftz.f32 %0, %1;" : "=f"(y) : "f"(x));
    return y;
}
__device__ __forceinline__ uint32_t pack_bf16(float lo, float hi) {
    uint32_t r;
    asm("cvt.rn.bf16x2.f32 %0, %1, %2;" : "=r"(r) : "f"(hi), "f"(lo));
    return r;
}
__device__ __forceinline__ void ldsm_x4(uint32_t addr, uint32_t& r0, uint32_t& r1, uint32_t& r2, uint32_t& r3) {
    asm volatile("ldmatrix.sync.aligned.m8n8.x4.shared.b16 {%0, %1, %2, %3}, [%4];"
                 : "=r"(r0), "=r"(r1), "=r"(r2), "=r"(r3) : "r"(addr) : "memory");
}
__device__ __forceinline__ void stsm_x4(uint32_t addr, uint32_t r0, uint32_t r1, uint32_t r2, uint32_t r3) {
    asm volatile("stmatrix.sync.aligned.m8n8.x4.shared.b16 [%0], {%1, %2, %3, %4};"
                 ::"r"(addr), "r"(r0), "r"(r1), "r"(r2), "r"(r3) : "memory");
}

__device__ __forceinline__ void mma_16816(float* d, const uint32_t* a, uint32_t b0, uint32_t b1) {
    asm volatile("mma.sync.aligned.m16n8k16.row.col.f32.bf16.bf16.f32 {%0, %1, %2, %3}, {%4, %5, %6, %7}, {%8, %9}, {%0, %1, %2, %3};"
                 : "+f"(d[0]), "+f"(d[1]), "+f"(d[2]), "+f"(d[3]) : "r"(a[0]), "r"(a[1]), "r"(a[2]), "r"(a[3]), "r"(b0), "r"(b1));
}

__device__ __forceinline__ uint64_t make_desc(uint32_t addr, uint32_t lbo_bytes, uint32_t sbo_bytes) {
    return (uint64_t)((addr & 0x3FFFF) >> 4) | ((uint64_t)(lbo_bytes >> 4) << 16) | ((uint64_t)(sbo_bytes >> 4) << 32) |
           (1ull << 62);
}

__global__ void __launch_bounds__(384, 1)
gqa_attn_kernel(const __grid_constant__ CUtensorMap tmQ, const __grid_constant__ CUtensorMap tmK,
                const __grid_constant__ CUtensorMap tmV, const __grid_constant__ CUtensorMap tmO,
                const char* __restrict__ gQ, const char* __restrict__ gK, const char* __restrict__ gV) {
    extern __shared__ __align__(1024) uint8_t smem_raw[];
    const uint32_t sbase = smem_u32(smem_raw);
    const uint32_t bars = sbase + kOffBar;
    const int warp = __shfl_sync(0xffffffffu, threadIdx.x >> 5, 0);
    const int lane = threadIdx.x & 31;
    const int cta = blockIdx.x;

    if (threadIdx.x == 256) {
        for (int i = 0; i < KS; i++) { mbar_init(bars + 8 * (kBarKFull + i), 1); mbar_init(bars + 8 * (kBarKEmpty + i), 8); }
        for (int i = 0; i < VS; i++) { mbar_init(bars + 8 * (kBarVFull + i), 1); mbar_init(bars + 8 * (kBarVEmpty + i), 8); }
        for (int i = 0; i < 2; i++) { mbar_init(bars + 8 * (kBarQFull + i), 1); mbar_init(bars + 8 * (kBarOFull + i), 4); }
        asm volatile("fence.mbarrier_init.release.cluster;" ::: "memory");
        fence_async_smem();
        mbar_expect_tx(bars + 8 * kBarQFull, kWgQBytes);
        tma_load_3d(sbase + kOffQ, &tmQ, bars + 8 * kBarQFull, 0, cta * kSeq, 0);
        mbar_expect_tx(bars + 8 * kBarKFull, kBlkBytes);
        tma_load_3d(sbase + kOffK, &tmK, bars + 8 * kBarKFull, 0, (cta >> 2) * kSeq, 0);
        mbar_expect_tx(bars + 8 * (kBarQFull + 1), kWgQBytes);
        tma_load_3d(sbase + kOffQ + kWgQBytes, &tmQ, bars + 8 * (kBarQFull + 1), 0, cta * kSeq + 64, 0);
    }
    __syncthreads();

    if (warp >= 8) {
        asm volatile("setmaxnreg.dec.sync.aligned.u32 24;");
        if (warp == 8 && lane == 0) {
            __nanosleep(SDELAY);
            for (int w = 0; w < kItems; w++) {
                const int kvrow = ((w * kGrid + cta) >> 2) * kSeq;
                for (int b = (w == 0); b < kNBlk; b++) {
                    mbar_wait(bars + 8 * (kBarKEmpty + b), (w & 1) ^ 1);
                    mbar_expect_tx(bars + 8 * (kBarKFull + b), kBlkBytes);
                    tma_load_3d(sbase + kOffK + b * kBlkBytes, &tmK, bars + 8 * (kBarKFull + b), 0, kvrow + b * kBlkN, 0);
                    if (w == 0 && b == 1) mbar_wait(bars + 8 * kBarKFull, 0);
                }
            }
        } else if (warp == 9 && lane == 0) {
            __nanosleep(SDELAY);
            for (int w = 0; w < kItems; w++) {
                const int kvrow = ((w * kGrid + cta) >> 2) * kSeq;
                for (int t = 0; t < kTilesPerItem; t++) {
                    for (int b = 0; b < kNBlk; b++) {
                        const int st = b & 1;
                        mbar_wait(bars + 8 * (kBarVEmpty + st), ((b >> 1) & 1) ^ 1);
                        mbar_expect_tx(bars + 8 * (kBarVFull + st), kBlkBytes);
                        tma_load_3d(sbase + kOffV + st * kBlkBytes, &tmV, bars + 8 * (kBarVFull + st), 0,
                                    kvrow + b * kBlkN, 0);
                        if (w == 0 && t == 0 && b == 0) mbar_wait(bars + 8 * kBarKFull, 0);
                        if (b == GPB_Q && (w | t) != 0 && w * 4 + t + 1 < kTiles) {
                            const int nt = w * 4 + t + 1;
                            bulk_prefetch(gQ + (size_t)(((nt >> 2) * kGrid + cta) * kSeq + (nt & 3) * 128) * 256, 2 * kWgQBytes);
                        }
                        if (t >= 2 && b == 0 && w + 1 < kItems) {
                            const int nrow = (((w + 1) * kGrid + cta) >> 2) * kSeq + (cta & 3) * kBlkN;
                            bulk_prefetch((t == 2 ? gK : gV) + (size_t)nrow * 256, kBlkBytes);
                        }
                    }
                }
            }
        } else if (warp >= 10 && lane == 0) {
            const int g = warp - 10;
            const uint32_t buf = sbase + kOffQ + g * kWgQBytes;
            const uint32_t qbar = bars + 8 * (kBarQFull + g), obar = bars + 8 * (kBarOFull + g);
            auto row_of = [&](int t) { return ((t >> 2) * kGrid + cta) * kSeq + (t & 3) * 128 + g * 64; };
            for (int t = 0; t <= kTiles; t++) {
                mbar_wait(obar, t & 1);
                if (t > 0) {
                    tma_store_3d(&tmO, buf, 0, row_of(t - 1), 0);
                    bulk_commit();
                    bulk_wait_read0();
                }
                if (t + 1 < kTiles) {
                    mbar_expect_tx(qbar, kWgQBytes);
                    tma_load_3d(buf, &tmQ, qbar, 0, row_of(t + 1), 0);
                }
            }
        }
    } else {
        asm volatile("setmaxnreg.inc.sync.aligned.u32 240;");
        const int wg = warp >> 2;
        int zero = blockIdx.y;
        const uint32_t qbar = bars + 8 * (kBarQFull + wg), obar = bars + 8 * (kBarOFull + wg);
        const uint32_t lrow = (warp & 3) * 16 + (lane & 7) + ((lane >> 3) & 1) * 8;
        const uint32_t laddr = sbase + kOffQ + wg * kWgQBytes + lrow * 128 + ((((lane >> 4) ^ (lane & 7))) << 4);
        const float c = 0.08838834764831845f * 1.4426950408889634f;

        if (wg == 1) bar_arrive(1, 256);

        const uint64_t kdesc0 = make_desc(sbase + kOffK, 16, 1024);
        const uint64_t vdesc0 = make_desc(sbase + kOffV, 16384, 1024);

        float S[64], O[64], T[32];
        uint32_t P[32], Qf[32];
        float mc0 = 0.f, mc1 = 0.f, l0 = 0.f, l1 = 0.f;
#pragma unroll
        for (int i = 0; i < 64; i++) { O[i] = 0.f; S[i] = 0.f; }
#pragma unroll
        for (int i = 0; i < 32; i++) P[i] = 0u;

        auto load_q = [&]() {
#pragma unroll
            for (int s = 0; s < 8; s++)
                ldsm_x4((laddr ^ ((2 * (s & 3)) << 4)) + (s >> 2) * 8192, Qf[4 * s], Qf[4 * s + 1], Qf[4 * s + 2],
                        Qf[4 * s + 3]);
        };
        mbar_wait(qbar, 0);
        load_q();
        __syncwarp();
        if (lane == 0) mbar_arrive(obar);

        auto issue_qk = [&](int blk) {
            const uint64_t kd = kdesc0 + (uint64_t)(blk * (kBlkBytes >> 4));
            wg_fence();
            wgmma_rs_init(S, Qf[0], Qf[1], Qf[2], Qf[3], kd);
#pragma unroll
            for (int s = 1; s < 8; s++)
                wgmma_rs<0>(S, Qf[4 * s], Qf[4 * s + 1], Qf[4 * s + 2], Qf[4 * s + 3],
                            kd + (uint64_t)((s >> 2) * (16384 >> 4) + (s & 3) * 2), 1);
            wg_commit();
        };
        auto issue_pv = [&](auto j0_c, int vs, int accumulate) {
            constexpr int kJ0 = decltype(j0_c)::value;
            const uint64_t vd = vdesc0 + (uint64_t)(vs * (kBlkBytes >> 4));
            fence_regs(O);
#pragma unroll
            for (int s = 0; s < 8; s++) {
                if (2 * s >= kJ0 && (s - kJ0 / 2) % GP == 0) {
                    if (s != 0) wg_commit();
#pragma unroll
                    for (int j = 2 * s; j < 2 * (s + GP) && j < 16; j++) {
                        const float e0 = ex2(T[2 * j]), e1 = ex2(T[2 * j + 1]);
                        l1 += e0 + e1;
                        P[2 * j + 1] = pack_bf16(e0, e1);
                    }
                    wg_fence();
                } else if (s == 0) {
                    wg_fence();
                }
                wgmma_rs<1>(O, P[4 * s], P[4 * s + 1], P[4 * s + 2], P[4 * s + 3], vd + (uint64_t)(s * (2048 >> 4)),
                            (s != 0) || accumulate);
            }
            wg_commit();
        };
        auto quad_max = [&](float v) {
            v = fmaxf(v, __shfl_xor_sync(0xffffffffu, v, 1));
            return fmaxf(v, __shfl_xor_sync(0xffffffffu, v, 2));
        };
        auto quad_sum = [&](float v) {
            v += __shfl_xor_sync(0xffffffffu, v, 1);
            return v + __shfl_xor_sync(0xffffffffu, v, 2);
        };
        auto row_max = [&](int r) {
            float x0 = fmaxf(S[r], S[r + 1]), x1 = fmaxf(S[4 + r], S[5 + r]);
#pragma unroll
            for (int j = 2; j < 16; j += 2) {
                x0 = fmaxf(x0, fmaxf(S[4 * j + r], S[4 * j + r + 1]));
                x1 = fmaxf(x1, fmaxf(S[4 * j + 4 + r], S[4 * j + 5 + r]));
            }
            return quad_max(fmaxf(x0, x1));
        };
        auto row_shift = [&](int r, float mc) {
#pragma unroll
            for (int j = 0; j < 16; j++) {
                S[4 * j + r]     = fmaf(S[4 * j + r], c, -mc);
                S[4 * j + r + 1] = fmaf(S[4 * j + r + 1], c, -mc);
            }
        };
        auto row_exp = [&](int r, float rs, int j0 = 0, int j1 = 16) {
#pragma unroll
            for (int j = 0; j < 16; j++) {
                if (j < j0 || j >= j1) continue;
                S[4 * j + r]     = ex2(S[4 * j + r]);
                S[4 * j + r + 1] = ex2(S[4 * j + r + 1]);
                rs += S[4 * j + r] + S[4 * j + r + 1];
            }
            return rs;
        };
        auto bits_max = [&](int r) {
            int a = __float_as_int(S[r]), b = __float_as_int(S[r + 1]);
#pragma unroll
            for (int j = 1; j < 15; j += 2) {
                a = __vimax3_s32(a, __float_as_int(S[4 * j + r]), __float_as_int(S[4 * j + r + 1]));
                b = __vimax3_s32(b, __float_as_int(S[4 * j + 4 + r]), __float_as_int(S[4 * j + 5 + r]));
            }
            a = __vimax3_s32(a, __float_as_int(S[60 + r]), __float_as_int(S[61 + r]));
            return max(a, b);
        };
        auto redo_exact = [&](int blk, float l0_old) {
            const uint32_t ka = sbase + kOffK + blk * kBlkBytes + (lane & 7) * 128;
            wg_wait<0>();
            fence_regs(O);
            fence_regs(P);
#pragma unroll
            for (int j = 0; j < 16; j++) {
                S[4 * j] = 0.f; S[4 * j + 1] = 0.f; S[4 * j + 2] = 0.f; S[4 * j + 3] = 0.f;
#pragma unroll
                for (int q = 0; q < 4; q++) {
                    uint32_t* b = &P[16 * (j & 1) + 4 * q];
                    ldsm_x4(ka + j * 1024 + (q >> 1) * 16384 + ((((lane >> 3) + 4 * (q & 1)) ^ (lane & 7)) << 4), b[0], b[1], b[2], b[3]);
                    mma_16816(&S[4 * j], &Qf[8 * q], b[0], b[1]);
                    mma_16816(&S[4 * j], &Qf[8 * q + 4], b[2], b[3]);
                }
                if (j & 1) sched_fence(zero);
            }
            float g0 = 0.f;
            if (blk == 0) {
                mc0 = row_max(0) * c;
                mc1 = row_max(2) * c;
            } else {
                const float m0 = fmaxf(mc0, row_max(0) * c), m1 = fmaxf(mc1, row_max(2) * c);
                g0 = ex2(mc0 - m0);
                const float g1 = ex2(mc1 - m1);
                mc0 = m0; mc1 = m1;
                l1 *= g1;
#pragma unroll
                for (int j = 0; j < 16; j++) {
                    O[4 * j] *= g0; O[4 * j + 1] *= g0;
                    O[4 * j + 2] *= g1; O[4 * j + 3] *= g1;
                }
                fence_regs(O);
            }
            row_shift(0, mc0);
            row_shift(2, mc1);
            l0 = row_exp(0, blk == 0 ? 0.f : l0_old * g0);
        };
        auto store_o_smem = [&]() {
#pragma unroll
            for (int s = 0; s < 8; s++) {
                const uint32_t r0 = pack_bf16(O[8 * s], O[8 * s + 1]);
                const uint32_t r1 = pack_bf16(O[8 * s + 2], O[8 * s + 3]);
                const uint32_t r2 = pack_bf16(O[8 * s + 4], O[8 * s + 5]);
                const uint32_t r3 = pack_bf16(O[8 * s + 6], O[8 * s + 7]);
                stsm_x4((laddr ^ ((2 * (s & 3)) << 4)) + (s >> 2) * 8192, r0, r1, r2, r3);
            }
        };
        auto publish_o = [&]() {
            fence_async_smem();
            __syncwarp();
            if (lane == 0) mbar_arrive(obar);
        };
        auto scale_o = [&](float f0, float f1) {
#pragma unroll
            for (int j = 0; j < 16; j++) {
                O[4 * j] *= f0; O[4 * j + 1] *= f0;
                O[4 * j + 2] *= f1; O[4 * j + 3] *= f1;
            }
        };
        auto pack_p = [&](auto j0_c) {
            constexpr int kJ0 = decltype(j0_c)::value;
#pragma unroll
            for (int j = 0; j < 16; j++) {
                P[2 * j] = pack_bf16(S[4 * j], S[4 * j + 1]);
                if (j < kJ0) {
                    P[2 * j + 1] = pack_bf16(S[4 * j + 2], S[4 * j + 3]);
                } else {
                    T[2 * j] = S[4 * j + 2];
                    T[2 * j + 1] = S[4 * j + 3];
                }
            }
        };
        auto fence_pt = [&](auto j0_c) {
            constexpr int kJ0 = decltype(j0_c)::value;
#pragma unroll
            for (int j = 0; j < 16; j++) {
                asm volatile("" : "+r"(P[2 * j])::"memory");
                if (j < kJ0) {
                    asm volatile("" : "+r"(P[2 * j + 1])::"memory");
                } else {
                    asm volatile("" : "+f"(T[2 * j]), "+f"(T[2 * j + 1])::"memory");
                }
            }
        };

        float f0 = 1.f, f1 = 1.f;
        auto step = [&](auto blk_c, int tile) {
            constexpr int blk = decltype(blk_c)::value;
            constexpr int vs = (blk + 1) & 1;
            constexpr int vph = ((blk + 3) >> 1) & 1;
            constexpr int jp = j0_of((blk + 3) & 3), jc = j0_of(blk);
            const uint32_t vfull = bars + 8 * (kBarVFull + vs);
            bar_sync(1 + wg, 256);
            const bool v_ok = mbar_try(vfull, vph);
            if ((tile & 3) == 0) mbar_wait(bars + 8 * (kBarKFull + blk), (tile >> 2) & 1);
            issue_qk(blk);
            if (blk == 1 && tile > 0) {
                scale_o(f0, f1);
                store_o_smem();
            }
            if (blk == 3 && tile + 1 < kTiles) mbar_wait(qbar, (tile + 1) & 1);
            if (!v_ok) mbar_wait(vfull, vph);
            issue_pv(IC<jp>{}, vs, blk != 1);
            asm volatile("" : "+f"(l1)::"memory");
            bar_arrive(2 - wg, 256);
            if (blk == 1 && tile > 0) publish_o();
            sched_fence(zero);
            wg_wait<pv_groups(jp)>();
            fence_regs(S);
            int amax = 0;
            const float l0_old = l0;
            if (blk == 0) {
                f0 = l0; f1 = l1;
                l0 = 0.f; l1 = 0.f;
                row_shift(0, mc0);
                f0 = rcp(quad_sum(f0));
                f1 = rcp(quad_sum(f1));
            } else {
                row_shift(0, mc0);
            }
            l0 = row_exp(0, l0);
            row_shift(2, mc1);
            amax = bits_max(2);
            bool redo = amax > 0x41400000 || !(l0 <= 4096.f);
            if (blk == 0) redo = redo || l0 < 2.3283064365386963e-10f || (amax < 0 && amax > (int)0xC2200000);
            if (__builtin_expect(__any_sync(0xffffffffu, redo), 0)) redo_exact(blk, l0_old);
            if ((tile & 3) == 3 && lane == 0) mbar_arrive(bars + 8 * (kBarKEmpty + blk));
            fence_regs(S);
            sched_fence(zero);
            wg_wait<0>();
            fence_regs(O);
            fence_regs(P);
            if (lane == 0) mbar_arrive(bars + 8 * (kBarVEmpty + vs));
            if (blk == 3) load_q();
            l1 = row_exp(2, l1, 0, jc);
            pack_p(IC<jc>{});
            fence_regs(O);
            fence_pt(IC<jc>{});
            sched_fence(zero);
        };

        bar_sync(1 + wg, 256);
        mbar_wait(bars + 8 * (kBarKFull + 0), 0);
        issue_qk(0);
        bar_arrive(2 - wg, 256);
        wg_wait<0>();
        fence_regs(S);
        mc0 = row_max(0) * c;
        mc1 = row_max(2) * c;
        row_shift(0, mc0);
        row_shift(2, mc1);
        l0 = row_exp(0, 0.f);
        l1 = row_exp(2, 0.f, 0, j0_of(0));
        pack_p(IC<j0_of(0)>{});
        fence_pt(IC<j0_of(0)>{});

#pragma unroll 1
        for (int tile = 0;; tile++) {
            step(IC<1>{}, tile);
            step(IC<2>{}, tile);
            step(IC<3>{}, tile);
            if (tile == kTiles - 1) break;
            step(IC<0>{}, tile + 1);
        }
        if (wg == 0) bar_sync(1, 256);
        mbar_wait(bars + 8 * (kBarVFull + 1), 1);
        issue_pv(IC<j0_of(3)>{}, 1, 1);
        f0 = rcp(quad_sum(l0));
        f1 = rcp(quad_sum(l1));
        wg_wait<0>();
        fence_regs(O);
        scale_o(f0, f1);
        store_o_smem();
        publish_o();
    }
}

typedef CUresult (*PFN_encodeTiled)(CUtensorMap*, CUtensorMapDataType, cuuint32_t, void*, const cuuint64_t*,
                                    const cuuint64_t*, const cuuint32_t*, const cuuint32_t*, CUtensorMapInterleave,
                                    CUtensorMapSwizzle, CUtensorMapL2promotion, CUtensorMapFloatOOBfill);

bool make_map(PFN_encodeTiled enc, CUtensorMap* tm, const void* ptr, uint64_t rows, uint32_t box_rows) {
    cuuint64_t dims[3] = {64, rows, 2};
    cuuint64_t strides[2] = {256, 128};
    cuuint32_t box[3] = {64, box_rows, 2};
    cuuint32_t estr[3] = {1, 1, 1};
    return enc(tm, CU_TENSOR_MAP_DATA_TYPE_BFLOAT16, 3, const_cast<void*>(ptr), dims, strides, box, estr,
               CU_TENSOR_MAP_INTERLEAVE_NONE, CU_TENSOR_MAP_SWIZZLE_128B, CU_TENSOR_MAP_L2_PROMOTION_L2_256B,
               CU_TENSOR_MAP_FLOAT_OOB_FILL_NONE) == CUDA_SUCCESS;
}

}

extern "C" void kernel_launch(void* const* d_in, const int* in_sizes, int n_in, void* d_out, int out_size) {
    static PFN_encodeTiled enc = nullptr;
    if (!enc) {
        void* fn = nullptr;
        cudaDriverEntryPointQueryResult qres;
        cudaGetDriverEntryPoint("cuTensorMapEncodeTiled", &fn, cudaEnableDefault, &qres);
        enc = (PFN_encodeTiled)fn;
        cudaFuncSetAttribute(gqa_attn_kernel, cudaFuncAttributeMaxDynamicSharedMemorySize, kSmemBytes);
    }
    CUtensorMap tq, tk, tv, to;
    make_map(enc, &tq, d_in[0], 16ull * 32 * 512, 64);
    make_map(enc, &tk, d_in[1], 16ull * 8 * 512, kBlkN);
    make_map(enc, &tv, d_in[2], 16ull * 8 * 512, kBlkN);
    make_map(enc, &to, d_out, 16ull * 32 * 512, 64);
    gqa_attn_kernel<<<kGrid, 384, kSmemBytes>>>(tq, tk, tv, to, (const char*)d_in[0], (const char*)d_in[1], (const char*)d_in[2]);
}
```
